```python
import torch

def _softmax(x, axis=-1):
    return torch.softmax(x, dim=axis)
def _gelu(x):
    return torch.nn.functional.gelu(x, approximate="tanh")
def _silu(x):
    return torch.nn.functional.silu(x)
def _sigmoid(x):
    return torch.sigmoid(x)
def _layernorm(x, axis=-1, eps=1e-5):
    m = x.mean(dim=axis, keepdim=True)
    v = x.var(dim=axis, keepdim=True, unbiased=False)
    return (x - m) / torch.sqrt(v + eps)
def _scatter_add(tgt, idx, src, axis=0):
    return tgt.clone().index_add_(axis, idx, src)
def _segment_sum(src, seg, n):
    out = torch.zeros((n,) + src.shape[1:], dtype=src.dtype)
    return out.index_add_(0, seg, src)
def _pad(x, pw):
    flat = tuple(v for pair in reversed(pw) for v in pair)
    return torch.nn.functional.pad(x, flat)

kernel_name = 'recurrent_scan__linear_kernel_hedgehog__glu_gated_swiglu__prompt'

def setup_inputs():

    _w = (lambda a: (lambda t: t.to(torch.bfloat16) if t.is_floating_point() else t)(torch.as_tensor(a)))
    def _A_setup():
        B, S, D, H = 1, 2048, 512, 32
        Dh = D // H
        return {
            "x": _w((lambda *s: torch.randn(*s, dtype=torch.bfloat16) * 0.05)(B, S, D)),
            "wqkv": _w((lambda *s: torch.randn(*s, dtype=torch.bfloat16) * 0.8)(D, 3 * D)),
            "w_phi": _w((lambda *s: torch.randn(*s, dtype=torch.bfloat16) * 0.8)(H, Dh, Dh) * (Dh ** -0.5)),
            "wo": _w((lambda *s: torch.randn(*s, dtype=torch.bfloat16) * 0.8)(D, D)),
        }
    _A_in = _A_setup()

    def _B_setup():
        B, S, D, F = 1, 2048, 512, 1376
        return {
            "x": _w((lambda *s: torch.randn(*s, dtype=torch.bfloat16) * 0.05)(B, S, D)),
            "w1": _w((lambda *s: torch.randn(*s, dtype=torch.bfloat16) * 0.2)(D, F) * (2.0 / D) ** 0.5),
            "w3": _w((lambda *s: torch.randn(*s, dtype=torch.bfloat16) * 0.2)(D, F) * (2.0 / D) ** 0.5),
            "w2": _w((lambda *s: torch.randn(*s, dtype=torch.bfloat16) * 0.2)(F, D) * (2.0 / F) ** 0.5),
        }
    _B_in = _B_setup()

    return {
        "A_x": _A_in["x"],
        "A_wqkv": _A_in["wqkv"],
        "A_w_phi": _A_in["w_phi"],
        "A_wo": _A_in["wo"],
        "B_x": _B_in["x"],
        "B_w1": _B_in["w1"],
        "B_w3": _B_in["w3"],
        "B_w2": _B_in["w2"],
    }

def reference(A_x, A_wqkv, A_w_phi, A_wo, B_x, B_w1, B_w3, B_w2):
    def _A_ref(x, wqkv, w_phi, wo):
        B, S, D = x.shape
        H = 32; Dh = D // H
        qkv = (lambda x, *d: x.permute(*d))((x @ wqkv).reshape(B, S, 3, H, Dh), 2, 0, 3, 1, 4)
        q, k, v = qkv[0], qkv[1], qkv[2]
        pq = torch.einsum("bhsd,hdf->bhsf", q, w_phi)
        pk = torch.einsum("bhsd,hdf->bhsf", k, w_phi)
        phi_q = torch.concatenate([_softmax(pq, axis=-1), _softmax(-pq, axis=-1)], axis=-1)
        phi_k = torch.concatenate([_softmax(pk, axis=-1), _softmax(-pk, axis=-1)], axis=-1)
        kv = torch.einsum("bhsf,bhsd->bhfd", phi_k, v)
        z  = torch.einsum("bhsf->bhf", phi_k)
        num = torch.einsum("bhqf,bhfd->bhqd", phi_q, kv)
        den = torch.einsum("bhqf,bhf->bhq", phi_q, z)[..., None] + 1e-6
        o = num / den
        return (lambda x, *d: x.permute(*d))(o, 0, 2, 1, 3).reshape(B, S, D) @ wo

    def _B_ref(x, w1, w3, w2):
        gate = torch.einsum("bsd,df->bsf", x, w1)
        up = torch.einsum("bsd,df->bsf", x, w3)
        h = _silu(gate) * up
        out = torch.einsum("bsf,fd->bsd", h, w2)
        return out

    x = A_x
    xn = _layernorm(x, axis=-1)
    s = _A_ref(xn, A_wqkv, A_w_phi, A_wo)
    g = _silu(_B_ref(xn, B_w1, B_w3, B_w2))
    return x + s * g
```

```cpp
#include <cuda_runtime.h>
#include <cuda_bf16.h>
#include <cuda.h>
#include <stdint.h>

#define DEVI __device__ __forceinline__

namespace hk {

constexpr int SEQ = 2048, DM = 512, FF = 1376;
constexpr int ACT_W = 2048;
constexpr int NCTA = 128;

constexpr uint32_t OFF_W    = 0;
constexpr uint32_t OFF_A    = 131072;
constexpr uint32_t OFF_STG  = 196608;
constexpr uint32_t OFF_KVF  = 212992;
constexpr uint32_t OFF_WPF  = 219136;
constexpr uint32_t OFF_BAR  = 221184;
constexpr uint32_t OFF_RAW  = OFF_BAR + 512;
constexpr uint32_t SMEM_BYTES = OFF_RAW + 8704 + 1024;

enum : uint32_t {
  B_FULL = 0, B_EMPTY = 12, B_XFULL = 24  , B_XFREE = 28, B_AFREE = 29, B_STGFULL = 30  , B_STGEMPTY = 32  ,
  B_KVREADY = 34, B_WPREADY = 35, B_XRES = 36, B_TOK = 39, B_X1FREE = 40, B_KVDONE = 41,
  B_RAWFULL = 42, B_AGRP = 43  , B_FULL2 = 47  , B_EMPTY2 = 51  , B_COUNT = 55
};

__device__ __nv_bfloat16 g_act[(size_t)SEQ * ACT_W];
__device__ float    g_kv[2][32][512 + 32];
__device__ unsigned g_kvflag[8 * 32];
__device__ unsigned g_aflag[16 * 8 * 4 * 8];
__device__ unsigned g_epoch[NCTA];

#define TS(slot) do {} while (0)
#define TSP(slot) do {} while (0)
#define TS3(i) do {} while (0)
#define TS2(i) do {} while (0)

struct Params {
  CUtensorMap x, x3, wqkv, w1, w3, wo, w2, act_st, w1t, w3t, w2t, act_t;
};

DEVI uint32_t smem_u32(const void* p) { return (uint32_t)__cvta_generic_to_shared(p); }
DEVI void mbar_init(uint32_t a, uint32_t c) { asm volatile("mbarrier.init.shared::cta.b64 [%0], %1;" ::"r"(a), "r"(c)); }
DEVI void mbar_expect_tx(uint32_t a, uint32_t b) {
  asm volatile("mbarrier.arrive.expect_tx.shared::cta.b64 _, [%0], %1;" ::"r"(a), "r"(b) : "memory");
}
DEVI void mbar_wait(uint32_t a, uint32_t ph) {
  asm volatile("{\n.reg .pred p;\n.reg .u32 c;\nmov.u32 c, 0;\n"
               "LAB_WAIT:\nmbarrier.try_wait.parity.shared::cta.b64 p, [%0], %1;\n@p bra LAB_DONE;\n"
               "add.u32 c, c, 1;\nsetp.lt.u32 p, c, 200000;\n@p bra LAB_WAIT;\nLAB_DONE:\n}\n"
               ::"r"(a), "r"(ph) : "memory");
}
DEVI void mbar_arrive(uint32_t a) { asm volatile("mbarrier.arrive.shared::cta.b64 _, [%0];" ::"r"(a) : "memory"); }
DEVI uint32_t mapa(uint32_t a, uint32_t cta) {
  uint32_t r; asm volatile("mapa.shared::cluster.u32 %0, %1, %2;" : "=r"(r) : "r"(a), "r"(cta)); return r;
}
DEVI void mbar_arrive_cluster(uint32_t ra) {
  asm volatile("mbarrier.arrive.shared::cluster.b64 _, [%0];" ::"r"(ra) : "memory");
}
DEVI void tma_ld(uint32_t dst, const CUtensorMap* m, int c0, int c1, uint32_t bar) {
  asm volatile("cp.async.bulk.tensor.2d.shared::cluster.global.mbarrier::complete_tx::bytes [%0], [%1, {%3, %4}], [%2];"
               ::"r"(dst), "l"(m), "r"(bar), "r"(c0), "r"(c1) : "memory");
}
DEVI void tma_ld3(uint32_t dst, const CUtensorMap* m, int c0, int c1, int c2, uint32_t bar) {
  asm volatile("cp.async.bulk.tensor.3d.shared::cluster.global.mbarrier::complete_tx::bytes [%0], [%1, {%3, %4, %5}], [%2];"
               ::"r"(dst), "l"(m), "r"(bar), "r"(c0), "r"(c1), "r"(c2) : "memory");
}
DEVI void bulk_ld(uint32_t dst, const void* src, uint32_t bytes, uint32_t bar) {
  asm volatile("cp.async.bulk.shared::cluster.global.mbarrier::complete_tx::bytes [%0], [%1], %2, [%3];"
               ::"r"(dst), "l"(src), "r"(bytes), "r"(bar) : "memory");
}
DEVI void tma_ld_mc(uint32_t dst, const CUtensorMap* m, int c0, int c1, uint32_t bar, uint16_t mask) {
  asm volatile("cp.async.bulk.tensor.2d.shared::cluster.global.mbarrier::complete_tx::bytes.multicast::cluster "
               "[%0], [%1, {%3, %4}], [%2], %5;"
               ::"r"(dst), "l"(m), "r"(bar), "r"(c0), "r"(c1), "h"(mask) : "memory");
}
DEVI void tma_st(const CUtensorMap* m, int c0, int c1, uint32_t src) {
  asm volatile("cp.async.bulk.tensor.2d.global.shared::cta.bulk_group [%0, {%2, %3}], [%1];"
               ::"l"(m), "r"(src), "r"(c0), "r"(c1) : "memory");
}
DEVI void bulk_commit() { asm volatile("cp.async.bulk.commit_group;" ::: "memory"); }
DEVI void bulk_wait_read() { asm volatile("cp.async.bulk.wait_group.read 0;" ::: "memory"); }
DEVI void bulk_wait_all() { asm volatile("cp.async.bulk.wait_group 0;" ::: "memory"); }
DEVI void fence_async_smem() { asm volatile("fence.proxy.async.shared::cta;" ::: "memory"); }
DEVI void fence_async_all() { asm volatile("fence.proxy.async.global;" ::: "memory"); }
DEVI void prefetch_tmap(const CUtensorMap* m) { asm volatile("prefetch.tensormap [%0];" ::"l"(m) : "memory"); }
DEVI void l2_prefetch(const void* p, uint32_t bytes) {
  asm volatile("cp.async.bulk.prefetch.L2.global [%0], %1;" ::"l"(p), "r"(bytes) : "memory");
}
DEVI void cluster_wait() { asm volatile("barrier.cluster.wait.acquire.aligned;" ::: "memory"); }
DEVI void named_bar(int id, int n) { asm volatile("bar.sync %0, %1;" ::"r"(id), "r"(n) : "memory"); }
DEVI unsigned ld_acquire(const unsigned* p) {
  unsigned v; asm volatile("ld.acquire.gpu.global.u32 %0, [%1];" : "=r"(v) : "l"(p) : "memory"); return v;
}
DEVI void red_release_add(unsigned* p, unsigned v) {
  asm volatile("red.release.gpu.global.add.u32 [%0], %1;" ::"l"(p), "r"(v) : "memory");
}
DEVI void red_relaxed_add(unsigned* p, unsigned v) {
  asm volatile("red.relaxed.gpu.global.add.u32 [%0], %1;" ::"l"(p), "r"(v) : "memory");
}
DEVI void red_add_v2(float* p, float a, float b) {
  asm volatile("red.relaxed.gpu.global.add.v2.f32 [%0], {%1, %2};" ::"l"(p), "f"(a), "f"(b) : "memory");
}
DEVI void red_add(float* p, float a) { asm volatile("red.relaxed.gpu.global.add.f32 [%0], %1;" ::"l"(p), "f"(a) : "memory"); }
DEVI void flag_wait(const unsigned* p, unsigned target) {
  int it = 0;
  while ((int)(ld_acquire(p) - target) < 0) { __nanosleep(32); if (++it > 200000) break; }
}
DEVI void ldsm_x4(uint32_t& r0, uint32_t& r1, uint32_t& r2, uint32_t& r3, uint32_t a) {
  asm volatile("ldmatrix.sync.aligned.m8n8.x4.shared.b16 {%0, %1, %2, %3}, [%4];"
               : "=r"(r0), "=r"(r1), "=r"(r2), "=r"(r3) : "r"(a) : "memory");
}
DEVI void stsm_x4(uint32_t a, uint32_t r0, uint32_t r1, uint32_t r2, uint32_t r3) {
  asm volatile("stmatrix.sync.aligned.m8n8.x4.shared.b16 [%0], {%1, %2, %3, %4};"
               ::"r"(a), "r"(r0), "r"(r1), "r"(r2), "r"(r3) : "memory");
}
DEVI uint4 lds128(uint32_t a) {
  uint4 v; asm volatile("ld.shared.v4.u32 {%0, %1, %2, %3}, [%4];" : "=r"(v.x), "=r"(v.y), "=r"(v.z), "=r"(v.w) : "r"(a) : "memory");
  return v;
}
DEVI float4 lds128f(uint32_t a) {
  float4 v; asm volatile("ld.shared.v4.f32 {%0, %1, %2, %3}, [%4];" : "=f"(v.x), "=f"(v.y), "=f"(v.z), "=f"(v.w) : "r"(a) : "memory");
  return v;
}
DEVI void sts128(uint32_t a, uint32_t x, uint32_t y, uint32_t z, uint32_t w) {
  asm volatile("st.shared.v4.u32 [%0], {%1, %2, %3, %4};" ::"r"(a), "r"(x), "r"(y), "r"(z), "r"(w) : "memory");
}
DEVI float lds32f(uint32_t a) { float v; asm volatile("ld.shared.f32 %0, [%1];" : "=f"(v) : "r"(a) : "memory"); return v; }
DEVI uint32_t lds32(uint32_t a) { uint32_t v; asm volatile("ld.shared.u32 %0, [%1];" : "=r"(v) : "r"(a) : "memory"); return v; }
DEVI void sts32(uint32_t a, uint32_t v) { asm volatile("st.shared.u32 [%0], %1;" ::"r"(a), "r"(v) : "memory"); }
DEVI void mma16816(float (&c)[4], uint32_t a0, uint32_t a1, uint32_t a2, uint32_t a3, uint32_t b0, uint32_t b1) {
  asm("mma.sync.aligned.m16n8k16.row.col.f32.bf16.bf16.f32 {%0, %1, %2, %3}, {%4, %5, %6, %7}, {%8, %9}, {%0, %1, %2, %3};"
               : "+f"(c[0]), "+f"(c[1]), "+f"(c[2]), "+f"(c[3]) : "r"(a0), "r"(a1), "r"(a2), "r"(a3), "r"(b0), "r"(b1));
}
DEVI uint32_t hmax2_bf16(uint32_t a, uint32_t b) { uint32_t r; asm("max.bf16x2 %0, %1, %2;" : "=r"(r) : "r"(a), "r"(b)); return r; }
DEVI uint32_t hmin2_bf16(uint32_t a, uint32_t b) { uint32_t r; asm("min.bf16x2 %0, %1, %2;" : "=r"(r) : "r"(a), "r"(b)); return r; }
DEVI void stg128(void* p, uint4 v) { asm volatile("st.global.v4.u32 [%0], {%1, %2, %3, %4};" ::"l"(p), "r"(v.x), "r"(v.y), "r"(v.z), "r"(v.w) : "memory"); }
DEVI void wg_fence() { asm volatile("wgmma.fence.sync.aligned;" ::: "memory"); }
DEVI void wg_commit() { asm volatile("wgmma.commit_group.sync.aligned;" ::: "memory"); }
template <int N> DEVI void wg_wait() { asm volatile("wgmma.wait_group.sync.aligned %0;" ::"n"(N) : "memory"); }

DEVI uint32_t pack2(float a, float b) {
  uint32_t r; asm("cvt.rn.bf16x2.f32 %0, %1, %2;" : "=r"(r) : "f"(b), "f"(a)); return r;
}
DEVI float bf_lo(uint32_t v) { return __uint_as_float(v << 16); }
DEVI float bf_hi(uint32_t v) { return __uint_as_float(v & 0xffff0000u); }
DEVI float bf_round(float a) { return bf_lo(pack2(a, a)); }
DEVI uint32_t hsub2_bf16(uint32_t a, uint32_t b) {
  uint32_t r; asm("sub.rn.bf16x2 %0, %1, %2;" : "=r"(r) : "r"(a), "r"(b)); return r;
}
DEVI float ex2(float x) { float r; asm("ex2.approx.ftz.f32 %0, %1;" : "=f"(r) : "f"(x)); return r; }
DEVI float rcp(float x) { float r; asm("rcp.approx.ftz.f32 %0, %1;" : "=f"(r) : "f"(x)); return r; }
constexpr float L2E = 1.4426950408889634f;
DEVI float silu_f(float x) { return x * rcp(1.0f + ex2(-L2E * x)); }

template <int OFF, uint32_t HI> DEVI void wgmma_rs_n128(float (&d)[64], uint32_t a0, uint32_t a1, uint32_t a2, uint32_t a3, uint32_t blo) {
  asm volatile("{\n.reg .pred p;\n.reg .b32 lo;\n.reg .b64 db;\nsetp.ne.b32 p, 1, 0;\n"
    "add.s32 lo, %68, %69;\nmov.b64 db, {lo, %70};\n"
    "wgmma.mma_async.sync.aligned.m64n128k16.f32.bf16.bf16 "
    "{%0, %1, %2, %3, %4, %5, %6, %7, %8, %9, %10, %11, %12, %13, %14, %15, %16, %17, %18, %19, %20, %21, %22, %23, %24, %25, %26, %27, %28, %29, %30, %31, %32, %33, %34, %35, %36, %37, %38, %39, %40, %41, %42, %43, %44, %45, %46, %47, %48, %49, %50, %51, %52, %53, %54, %55, %56, %57, %58, %59, %60, %61, %62, %63}, "
    "{%64, %65, %66, %67}, db, p, 1, 1, 1;\n}\n"
    : "+f"(d[0]), "+f"(d[1]), "+f"(d[2]), "+f"(d[3]), "+f"(d[4]), "+f"(d[5]), "+f"(d[6]), "+f"(d[7]), "+f"(d[8]), "+f"(d[9]), "+f"(d[10]), "+f"(d[11]), "+f"(d[12]), "+f"(d[13]), "+f"(d[14]), "+f"(d[15]), "+f"(d[16]), "+f"(d[17]), "+f"(d[18]), "+f"(d[19]), "+f"(d[20]), "+f"(d[21]), "+f"(d[22]), "+f"(d[23]), "+f"(d[24]), "+f"(d[25]), "+f"(d[26]), "+f"(d[27]), "+f"(d[28]), "+f"(d[29]), "+f"(d[30]), "+f"(d[31]), "+f"(d[32]), "+f"(d[33]), "+f"(d[34]), "+f"(d[35]), "+f"(d[36]), "+f"(d[37]), "+f"(d[38]), "+f"(d[39]), "+f"(d[40]), "+f"(d[41]), "+f"(d[42]), "+f"(d[43]), "+f"(d[44]), "+f"(d[45]), "+f"(d[46]), "+f"(d[47]), "+f"(d[48]), "+f"(d[49]), "+f"(d[50]), "+f"(d[51]), "+f"(d[52]), "+f"(d[53]), "+f"(d[54]), "+f"(d[55]), "+f"(d[56]), "+f"(d[57]), "+f"(d[58]), "+f"(d[59]), "+f"(d[60]), "+f"(d[61]), "+f"(d[62]), "+f"(d[63])
    : "r"(a0), "r"(a1), "r"(a2), "r"(a3), "r"(blo), "n"(OFF), "n"(HI));
}
template <int OFF, uint32_t HI> DEVI void wgmma_rs_n128_first(float (&d)[64], uint32_t a0, uint32_t a1, uint32_t a2, uint32_t a3, uint32_t blo) {
  asm volatile("{\n.reg .pred p;\n.reg .b32 lo;\n.reg .b64 db;\nsetp.ne.b32 p, 0, 0;\n"
    "add.s32 lo, %68, %69;\nmov.b64 db, {lo, %70};\n"
    "wgmma.mma_async.sync.aligned.m64n128k16.f32.bf16.bf16 "
    "{%0, %1, %2, %3, %4, %5, %6, %7, %8, %9, %10, %11, %12, %13, %14, %15, %16, %17, %18, %19, %20, %21, %22, %23, %24, %25, %26, %27, %28, %29, %30, %31, %32, %33, %34, %35, %36, %37, %38, %39, %40, %41, %42, %43, %44, %45, %46, %47, %48, %49, %50, %51, %52, %53, %54, %55, %56, %57, %58, %59, %60, %61, %62, %63}, "
    "{%64, %65, %66, %67}, db, p, 1, 1, 1;\n}\n"
    : "=f"(d[0]), "=f"(d[1]), "=f"(d[2]), "=f"(d[3]), "=f"(d[4]), "=f"(d[5]), "=f"(d[6]), "=f"(d[7]), "=f"(d[8]), "=f"(d[9]), "=f"(d[10]), "=f"(d[11]), "=f"(d[12]), "=f"(d[13]), "=f"(d[14]), "=f"(d[15]), "=f"(d[16]), "=f"(d[17]), "=f"(d[18]), "=f"(d[19]), "=f"(d[20]), "=f"(d[21]), "=f"(d[22]), "=f"(d[23]), "=f"(d[24]), "=f"(d[25]), "=f"(d[26]), "=f"(d[27]), "=f"(d[28]), "=f"(d[29]), "=f"(d[30]), "=f"(d[31]), "=f"(d[32]), "=f"(d[33]), "=f"(d[34]), "=f"(d[35]), "=f"(d[36]), "=f"(d[37]), "=f"(d[38]), "=f"(d[39]), "=f"(d[40]), "=f"(d[41]), "=f"(d[42]), "=f"(d[43]), "=f"(d[44]), "=f"(d[45]), "=f"(d[46]), "=f"(d[47]), "=f"(d[48]), "=f"(d[49]), "=f"(d[50]), "=f"(d[51]), "=f"(d[52]), "=f"(d[53]), "=f"(d[54]), "=f"(d[55]), "=f"(d[56]), "=f"(d[57]), "=f"(d[58]), "=f"(d[59]), "=f"(d[60]), "=f"(d[61]), "=f"(d[62]), "=f"(d[63])
    : "r"(a0), "r"(a1), "r"(a2), "r"(a3), "r"(blo), "n"(OFF), "n"(HI));
}
template <int OFF, uint32_t HI> DEVI void wgmma_rs_n64(float (&d)[32], uint32_t a0, uint32_t a1, uint32_t a2, uint32_t a3, uint32_t blo) {
  asm volatile("{\n.reg .pred p;\n.reg .b32 lo;\n.reg .b64 db;\nsetp.ne.b32 p, 1, 0;\n"
    "add.s32 lo, %36, %37;\nmov.b64 db, {lo, %38};\n"
    "wgmma.mma_async.sync.aligned.m64n64k16.f32.bf16.bf16 "
    "{%0, %1, %2, %3, %4, %5, %6, %7, %8, %9, %10, %11, %12, %13, %14, %15, %16, %17, %18, %19, %20, %21, %22, %23, %24, %25, %26, %27, %28, %29, %30, %31}, "
    "{%32, %33, %34, %35}, db, p, 1, 1, 1;\n}\n"
    : "+f"(d[0]), "+f"(d[1]), "+f"(d[2]), "+f"(d[3]), "+f"(d[4]), "+f"(d[5]), "+f"(d[6]), "+f"(d[7]), "+f"(d[8]), "+f"(d[9]), "+f"(d[10]), "+f"(d[11]), "+f"(d[12]), "+f"(d[13]), "+f"(d[14]), "+f"(d[15]), "+f"(d[16]), "+f"(d[17]), "+f"(d[18]), "+f"(d[19]), "+f"(d[20]), "+f"(d[21]), "+f"(d[22]), "+f"(d[23]), "+f"(d[24]), "+f"(d[25]), "+f"(d[26]), "+f"(d[27]), "+f"(d[28]), "+f"(d[29]), "+f"(d[30]), "+f"(d[31])
    : "r"(a0), "r"(a1), "r"(a2), "r"(a3), "r"(blo), "n"(OFF), "n"(HI));
}
template <int OFF, uint32_t HI> DEVI void wgmma_rs_n64_first(float (&d)[32], uint32_t a0, uint32_t a1, uint32_t a2, uint32_t a3, uint32_t blo) {
  asm volatile("{\n.reg .pred p;\n.reg .b32 lo;\n.reg .b64 db;\nsetp.ne.b32 p, 0, 0;\n"
    "add.s32 lo, %36, %37;\nmov.b64 db, {lo, %38};\n"
    "wgmma.mma_async.sync.aligned.m64n64k16.f32.bf16.bf16 "
    "{%0, %1, %2, %3, %4, %5, %6, %7, %8, %9, %10, %11, %12, %13, %14, %15, %16, %17, %18, %19, %20, %21, %22, %23, %24, %25, %26, %27, %28, %29, %30, %31}, "
    "{%32, %33, %34, %35}, db, p, 1, 1, 1;\n}\n"
    : "=f"(d[0]), "=f"(d[1]), "=f"(d[2]), "=f"(d[3]), "=f"(d[4]), "=f"(d[5]), "=f"(d[6]), "=f"(d[7]), "=f"(d[8]), "=f"(d[9]), "=f"(d[10]), "=f"(d[11]), "=f"(d[12]), "=f"(d[13]), "=f"(d[14]), "=f"(d[15]), "=f"(d[16]), "=f"(d[17]), "=f"(d[18]), "=f"(d[19]), "=f"(d[20]), "=f"(d[21]), "=f"(d[22]), "=f"(d[23]), "=f"(d[24]), "=f"(d[25]), "=f"(d[26]), "=f"(d[27]), "=f"(d[28]), "=f"(d[29]), "=f"(d[30]), "=f"(d[31])
    : "r"(a0), "r"(a1), "r"(a2), "r"(a3), "r"(blo), "n"(OFF), "n"(HI));
}
template <int OFF, uint32_t HI> DEVI void wgmma_rs_n48(float (&d)[24], uint32_t a0, uint32_t a1, uint32_t a2, uint32_t a3, uint32_t blo) {
  asm volatile("{\n.reg .pred p;\n.reg .b32 lo;\n.reg .b64 db;\nsetp.ne.b32 p, 1, 0;\n"
    "add.s32 lo, %28, %29;\nmov.b64 db, {lo, %30};\n"
    "wgmma.mma_async.sync.aligned.m64n48k16.f32.bf16.bf16 "
    "{%0, %1, %2, %3, %4, %5, %6, %7, %8, %9, %10, %11, %12, %13, %14, %15, %16, %17, %18, %19, %20, %21, %22, %23}, "
    "{%24, %25, %26, %27}, db, p, 1, 1, 1;\n}\n"
    : "+f"(d[0]), "+f"(d[1]), "+f"(d[2]), "+f"(d[3]), "+f"(d[4]), "+f"(d[5]), "+f"(d[6]), "+f"(d[7]), "+f"(d[8]), "+f"(d[9]), "+f"(d[10]), "+f"(d[11]), "+f"(d[12]), "+f"(d[13]), "+f"(d[14]), "+f"(d[15]), "+f"(d[16]), "+f"(d[17]), "+f"(d[18]), "+f"(d[19]), "+f"(d[20]), "+f"(d[21]), "+f"(d[22]), "+f"(d[23])
    : "r"(a0), "r"(a1), "r"(a2), "r"(a3), "r"(blo), "n"(OFF), "n"(HI));
}
template <int OFF, uint32_t HI> DEVI void wgmma_rs_n48_first(float (&d)[24], uint32_t a0, uint32_t a1, uint32_t a2, uint32_t a3, uint32_t blo) {
  asm volatile("{\n.reg .pred p;\n.reg .b32 lo;\n.reg .b64 db;\nsetp.ne.b32 p, 0, 0;\n"
    "add.s32 lo, %28, %29;\nmov.b64 db, {lo, %30};\n"
    "wgmma.mma_async.sync.aligned.m64n48k16.f32.bf16.bf16 "
    "{%0, %1, %2, %3, %4, %5, %6, %7, %8, %9, %10, %11, %12, %13, %14, %15, %16, %17, %18, %19, %20, %21, %22, %23}, "
    "{%24, %25, %26, %27}, db, p, 1, 1, 1;\n}\n"
    : "=f"(d[0]), "=f"(d[1]), "=f"(d[2]), "=f"(d[3]), "=f"(d[4]), "=f"(d[5]), "=f"(d[6]), "=f"(d[7]), "=f"(d[8]), "=f"(d[9]), "=f"(d[10]), "=f"(d[11]), "=f"(d[12]), "=f"(d[13]), "=f"(d[14]), "=f"(d[15]), "=f"(d[16]), "=f"(d[17]), "=f"(d[18]), "=f"(d[19]), "=f"(d[20]), "=f"(d[21]), "=f"(d[22]), "=f"(d[23])
    : "r"(a0), "r"(a1), "r"(a2), "r"(a3), "r"(blo), "n"(OFF), "n"(HI));
}
template <int OFF, uint32_t HI> DEVI void wgmma_rs_n24(float (&d)[12], uint32_t a0, uint32_t a1, uint32_t a2, uint32_t a3, uint32_t blo) {
  asm volatile("{\n.reg .pred p;\n.reg .b32 lo;\n.reg .b64 db;\nsetp.ne.b32 p, 1, 0;\n"
    "add.s32 lo, %16, %17;\nmov.b64 db, {lo, %18};\n"
    "wgmma.mma_async.sync.aligned.m64n24k16.f32.bf16.bf16 "
    "{%0, %1, %2, %3, %4, %5, %6, %7, %8, %9, %10, %11}, "
    "{%12, %13, %14, %15}, db, p, 1, 1, 1;\n}\n"
    : "+f"(d[0]), "+f"(d[1]), "+f"(d[2]), "+f"(d[3]), "+f"(d[4]), "+f"(d[5]), "+f"(d[6]), "+f"(d[7]), "+f"(d[8]), "+f"(d[9]), "+f"(d[10]), "+f"(d[11])
    : "r"(a0), "r"(a1), "r"(a2), "r"(a3), "r"(blo), "n"(OFF), "n"(HI));
}
template <int OFF, uint32_t HI> DEVI void wgmma_rs_n24_first(float (&d)[12], uint32_t a0, uint32_t a1, uint32_t a2, uint32_t a3, uint32_t blo) {
  asm volatile("{\n.reg .pred p;\n.reg .b32 lo;\n.reg .b64 db;\nsetp.ne.b32 p, 0, 0;\n"
    "add.s32 lo, %16, %17;\nmov.b64 db, {lo, %18};\n"
    "wgmma.mma_async.sync.aligned.m64n24k16.f32.bf16.bf16 "
    "{%0, %1, %2, %3, %4, %5, %6, %7, %8, %9, %10, %11}, "
    "{%12, %13, %14, %15}, db, p, 1, 1, 1;\n}\n"
    : "=f"(d[0]), "=f"(d[1]), "=f"(d[2]), "=f"(d[3]), "=f"(d[4]), "=f"(d[5]), "=f"(d[6]), "=f"(d[7]), "=f"(d[8]), "=f"(d[9]), "=f"(d[10]), "=f"(d[11])
    : "r"(a0), "r"(a1), "r"(a2), "r"(a3), "r"(blo), "n"(OFF), "n"(HI));
}
template <int OFF, uint32_t HI> DEVI void wgmma_rs_n16_first(float (&d)[8], uint32_t a0, uint32_t a1, uint32_t a2, uint32_t a3, uint32_t blo) {
  asm volatile("{\n.reg .pred p;\n.reg .b32 lo;\n.reg .b64 db;\nsetp.ne.b32 p, 0, 0;\n"
    "add.s32 lo, %12, %13;\nmov.b64 db, {lo, %14};\n"
    "wgmma.mma_async.sync.aligned.m64n16k16.f32.bf16.bf16 "
    "{%0, %1, %2, %3, %4, %5, %6, %7}, "
    "{%8, %9, %10, %11}, db, p, 1, 1, 1;\n}\n"
    : "=f"(d[0]), "=f"(d[1]), "=f"(d[2]), "=f"(d[3]), "=f"(d[4]), "=f"(d[5]), "=f"(d[6]), "=f"(d[7])
    : "r"(a0), "r"(a1), "r"(a2), "r"(a3), "r"(blo), "n"(OFF), "n"(HI));
}
template <int OFFA, int OFFB> DEVI void wgmma_ss_n64(float (&d)[32], uint32_t alo, uint32_t blo) {
  asm volatile("{\n.reg .pred p;\n.reg .b32 lo;\n.reg .b64 da, db;\nsetp.ne.b32 p, 1, 0;\n"
    "add.s32 lo, %32, %34;\nmov.b64 da, {lo, 0x40000040};\nadd.s32 lo, %33, %35;\nmov.b64 db, {lo, 0x40000040};\n"
    "wgmma.mma_async.sync.aligned.m64n64k16.f32.bf16.bf16 "
    "{%0, %1, %2, %3, %4, %5, %6, %7, %8, %9, %10, %11, %12, %13, %14, %15, %16, %17, %18, %19, %20, %21, %22, %23, %24, %25, %26, %27, %28, %29, %30, %31}, "
    "da, db, p, 1, 1, 0, 1;\n}\n"
    : "+f"(d[0]), "+f"(d[1]), "+f"(d[2]), "+f"(d[3]), "+f"(d[4]), "+f"(d[5]), "+f"(d[6]), "+f"(d[7]), "+f"(d[8]), "+f"(d[9]), "+f"(d[10]), "+f"(d[11]), "+f"(d[12]), "+f"(d[13]), "+f"(d[14]), "+f"(d[15]), "+f"(d[16]), "+f"(d[17]), "+f"(d[18]), "+f"(d[19]), "+f"(d[20]), "+f"(d[21]), "+f"(d[22]), "+f"(d[23]), "+f"(d[24]), "+f"(d[25]), "+f"(d[26]), "+f"(d[27]), "+f"(d[28]), "+f"(d[29]), "+f"(d[30]), "+f"(d[31])
    : "r"(alo), "r"(blo), "n"(OFFA), "n"(OFFB));
}
template <int OFFA, int OFFB> DEVI void wgmma_ss_n64_first(float (&d)[32], uint32_t alo, uint32_t blo) {
  asm volatile("{\n.reg .pred p;\n.reg .b32 lo;\n.reg .b64 da, db;\nsetp.ne.b32 p, 0, 0;\n"
    "add.s32 lo, %32, %34;\nmov.b64 da, {lo, 0x40000040};\nadd.s32 lo, %33, %35;\nmov.b64 db, {lo, 0x40000040};\n"
    "wgmma.mma_async.sync.aligned.m64n64k16.f32.bf16.bf16 "
    "{%0, %1, %2, %3, %4, %5, %6, %7, %8, %9, %10, %11, %12, %13, %14, %15, %16, %17, %18, %19, %20, %21, %22, %23, %24, %25, %26, %27, %28, %29, %30, %31}, "
    "da, db, p, 1, 1, 0, 1;\n}\n"
    : "=f"(d[0]), "=f"(d[1]), "=f"(d[2]), "=f"(d[3]), "=f"(d[4]), "=f"(d[5]), "=f"(d[6]), "=f"(d[7]), "=f"(d[8]), "=f"(d[9]), "=f"(d[10]), "=f"(d[11]), "=f"(d[12]), "=f"(d[13]), "=f"(d[14]), "=f"(d[15]), "=f"(d[16]), "=f"(d[17]), "=f"(d[18]), "=f"(d[19]), "=f"(d[20]), "=f"(d[21]), "=f"(d[22]), "=f"(d[23]), "=f"(d[24]), "=f"(d[25]), "=f"(d[26]), "=f"(d[27]), "=f"(d[28]), "=f"(d[29]), "=f"(d[30]), "=f"(d[31])
    : "r"(alo), "r"(blo), "n"(OFFA), "n"(OFFB));
}
template <int OFFA, int OFFB> DEVI void wgmma_tt_n40(float (&d)[20], uint32_t alo, uint32_t blo) {
  asm volatile("{\n.reg .pred p;\n.reg .b32 lo;\n.reg .b64 da, db;\nsetp.ne.b32 p, 1, 0;\n"
    "add.s32 lo, %20, %22;\nmov.b64 da, {lo, 0x40000040};\nadd.s32 lo, %21, %23;\nmov.b64 db, {lo, 0x40000040};\n"
    "wgmma.mma_async.sync.aligned.m64n40k16.f32.bf16.bf16 "
    "{%0, %1, %2, %3, %4, %5, %6, %7, %8, %9, %10, %11, %12, %13, %14, %15, %16, %17, %18, %19}, "
    "da, db, p, 1, 1, 1, 1;\n}\n"
    : "+f"(d[0]), "+f"(d[1]), "+f"(d[2]), "+f"(d[3]), "+f"(d[4]), "+f"(d[5]), "+f"(d[6]), "+f"(d[7]), "+f"(d[8]), "+f"(d[9]), "+f"(d[10]), "+f"(d[11]), "+f"(d[12]), "+f"(d[13]), "+f"(d[14]), "+f"(d[15]), "+f"(d[16]), "+f"(d[17]), "+f"(d[18]), "+f"(d[19])
    : "r"(alo), "r"(blo), "n"(OFFA), "n"(OFFB));
}
template <int OFFA, int OFFB> DEVI void wgmma_tt_n40_first(float (&d)[20], uint32_t alo, uint32_t blo) {
  asm volatile("{\n.reg .pred p;\n.reg .b32 lo;\n.reg .b64 da, db;\nsetp.ne.b32 p, 0, 0;\n"
    "add.s32 lo, %20, %22;\nmov.b64 da, {lo, 0x40000040};\nadd.s32 lo, %21, %23;\nmov.b64 db, {lo, 0x40000040};\n"
    "wgmma.mma_async.sync.aligned.m64n40k16.f32.bf16.bf16 "
    "{%0, %1, %2, %3, %4, %5, %6, %7, %8, %9, %10, %11, %12, %13, %14, %15, %16, %17, %18, %19}, "
    "da, db, p, 1, 1, 1, 1;\n}\n"
    : "=f"(d[0]), "=f"(d[1]), "=f"(d[2]), "=f"(d[3]), "=f"(d[4]), "=f"(d[5]), "=f"(d[6]), "=f"(d[7]), "=f"(d[8]), "=f"(d[9]), "=f"(d[10]), "=f"(d[11]), "=f"(d[12]), "=f"(d[13]), "=f"(d[14]), "=f"(d[15]), "=f"(d[16]), "=f"(d[17]), "=f"(d[18]), "=f"(d[19])
    : "r"(alo), "r"(blo), "n"(OFFA), "n"(OFFB));
}

#define WAIT_LN1 1
#define PF_MODE 2
DEVI int chunk_f0(int j) { return 176 * j - (j >= 4 ? 16 : 0); }

DEVI void hh_project_issue(const uint32_t (&a)[4][4], uint32_t wp_addr, float (&pp)[4][8]) {
  const uint32_t wlo = ((wp_addr & 0x3FFFF) >> 4) | (16u << 16);
  wg_fence();
  wgmma_rs_n16_first<0, 8>(pp[0], a[0][0], a[0][1], a[0][2], a[0][3], wlo);
  wgmma_rs_n16_first<32, 8>(pp[1], a[1][0], a[1][1], a[1][2], a[1][3], wlo);
  wgmma_rs_n16_first<64, 8>(pp[2], a[2][0], a[2][1], a[2][2], a[2][3], wlo);
  wgmma_rs_n16_first<96, 8>(pp[3], a[3][0], a[3][1], a[3][2], a[3][3], wlo);
  wg_commit();
}
DEVI void hh_project_finish(const float (&pp)[4][8], uint32_t (&r)[4][4], uint32_t (&mx)[4], uint32_t (&mn)[4]) {
#pragma unroll
  for (int h = 0; h < 4; h++) {
    const float* p = pp[h];
    r[h][0] = pack2(p[0], p[1]); r[h][1] = pack2(p[2], p[3]); r[h][2] = pack2(p[4], p[5]); r[h][3] = pack2(p[6], p[7]);
    const uint32_t xa = hmax2_bf16(r[h][0], r[h][2]), xb = hmax2_bf16(r[h][1], r[h][3]);
    const uint32_t ya = hmin2_bf16(r[h][0], r[h][2]), yb = hmin2_bf16(r[h][1], r[h][3]);
    mx[h] = hmax2_bf16(__byte_perm(xa, xb, 0x5410), __byte_perm(xa, xb, 0x7632));
    mn[h] = hmin2_bf16(__byte_perm(ya, yb, 0x5410), __byte_perm(ya, yb, 0x7632));
  }
#pragma unroll
  for (int s = 1; s <= 2; s <<= 1)
#pragma unroll
    for (int h = 0; h < 4; h++) {
      mx[h] = hmax2_bf16(mx[h], __shfl_xor_sync(0xffffffffu, mx[h], s));
      mn[h] = hmin2_bf16(mn[h], __shfl_xor_sync(0xffffffffu, mn[h], s));
    }
}
DEVI void hh_softmax2(const uint32_t (&r)[4][4], const uint32_t (&mx)[4], const uint32_t (&mn)[4], int h0,
                      uint32_t (&pos)[2][4], uint32_t (&neg)[2][4]) {
  float e[2][16], sm[2][4];
#pragma unroll
  for (int u = 0; u < 2; u++) {
    const int h = h0 + u;
    const float mxa = bf_lo(mx[h]) * -L2E, mxb = bf_hi(mx[h]) * -L2E, mna = bf_lo(mn[h]) * L2E, mnb = bf_hi(mn[h]) * L2E;
    const float va[4] = {bf_lo(r[h][0]), bf_hi(r[h][0]), bf_lo(r[h][2]), bf_hi(r[h][2])};
    const float vb[4] = {bf_lo(r[h][1]), bf_hi(r[h][1]), bf_lo(r[h][3]), bf_hi(r[h][3])};
#pragma unroll
    for (int i = 0; i < 4; i++) {
      e[u][i] = ex2(fmaf(va[i], L2E, mxa));      e[u][4 + i] = ex2(fmaf(vb[i], L2E, mxb));
      e[u][8 + i] = ex2(fmaf(va[i], -L2E, mna)); e[u][12 + i] = ex2(fmaf(vb[i], -L2E, mnb));
    }
#pragma unroll
    for (int c = 0; c < 4; c++) sm[u][c] = (e[u][4 * c] + e[u][4 * c + 1]) + (e[u][4 * c + 2] + e[u][4 * c + 3]);
  }
#pragma unroll
  for (int s = 1; s <= 2; s <<= 1)
#pragma unroll
    for (int u = 0; u < 2; u++)
#pragma unroll
      for (int c = 0; c < 4; c++) sm[u][c] += __shfl_xor_sync(0xffffffffu, sm[u][c], s);
#pragma unroll
  for (int u = 0; u < 2; u++) {
    const float ra = rcp(sm[u][0]), rb = rcp(sm[u][1]), rna = rcp(sm[u][2]), rnb = rcp(sm[u][3]);
    pos[u][0] = pack2(e[u][0] * ra, e[u][1] * ra);     pos[u][1] = pack2(e[u][4] * rb, e[u][5] * rb);
    pos[u][2] = pack2(e[u][2] * ra, e[u][3] * ra);     pos[u][3] = pack2(e[u][6] * rb, e[u][7] * rb);
    neg[u][0] = pack2(e[u][8] * rna, e[u][9] * rna);   neg[u][1] = pack2(e[u][12] * rnb, e[u][13] * rnb);
    neg[u][2] = pack2(e[u][10] * rna, e[u][11] * rna); neg[u][3] = pack2(e[u][14] * rnb, e[u][15] * rnb);
  }
}

DEVI uint32_t swiglu2(float g0, float g1, float u0, float u1, float c1, float r2) {
  const float s0 = rcp(1.0f + ex2(g0 * c1)), s1 = rcp(1.0f + ex2(g1 * c1));
  return pack2((g0 * u0) * (s0 * r2), (g1 * u1) * (s1 * r2));
}

__host__ __device__ constexpr uint32_t ring_slot(int n) { return n < 8 ? (n < 0 ? 0 : n) : (n - 8) % 12; }
__host__ __device__ constexpr uint32_t ring_par(int n) { return n < 8 ? 0u : ((n - 8) / 12 + (ring_slot(n) < 8u ? 1u : 0u)) & 1u; }

__global__ void __cluster_dims__(2, 1, 1) __launch_bounds__(384, 1)
fused_kernel(const __grid_constant__ Params P, const __nv_bfloat16* __restrict__ w_phi, __nv_bfloat16* __restrict__ out,
             const char* __restrict__ pf_wo, const char* __restrict__ pf_w2) {
  extern __shared__ uint8_t smem_raw[];
  const uint32_t sb = (smem_u32(smem_raw) + 1023u) & ~1023u;
  const uint32_t bar = sb + OFF_BAR;
  const int tid = threadIdx.x, warp = tid >> 5, lane = tid & 31;
  const int rank = blockIdx.x & 1, pair = blockIdx.x >> 1;
  const int ga = pair >> 3, j = pair & 7;
  const int ib = 2 * ga + rank;
  const int i2 = 2 * ga + (j >> 2);
  const int c2 = j & 3;
  const int f0 = chunk_f0(j);
  auto BAR = [&](uint32_t idx) { return bar + idx * 8; };

  if (tid == 288) {
    for (int s = 0; s < 4; s++) mbar_init(BAR(B_XFULL + s), 1);
    fence_async_smem();
    mbar_expect_tx(BAR(B_XFULL), 32768);
    tma_ld3(sb + OFF_W + 4 * 16384, &P.x3, 0, ib * 128, 0, BAR(B_XFULL));
    mbar_expect_tx(BAR(B_XFULL + 2), 32768);
    tma_ld3(sb + OFF_A, &P.x3, 0, ib * 128 + 64, 0, BAR(B_XFULL + 2));
    mbar_expect_tx(BAR(B_XFULL + 1), 32768);
    tma_ld3(sb + OFF_W + 6 * 16384, &P.x3, 0, ib * 128, 4, BAR(B_XFULL + 1));
    mbar_expect_tx(BAR(B_XFULL + 3), 32768);
    tma_ld3(sb + OFF_A + 32768, &P.x3, 0, ib * 128 + 64, 4, BAR(B_XFULL + 3));
    TSP(60);
  } else if (tid == 256) {
    for (int s = 0; s < 12; s++) { mbar_init(BAR(B_FULL + s), 1); mbar_init(BAR(B_EMPTY + s), 4); }
    mbar_init(BAR(B_XFREE), 8); mbar_init(BAR(B_AFREE), 16);
    for (int w = 0; w < 2; w++) { mbar_init(BAR(B_STGFULL + w), 4); mbar_init(BAR(B_STGEMPTY + w), 1); }
    mbar_init(BAR(B_KVREADY), 1); mbar_init(BAR(B_WPREADY), 1);
    mbar_init(BAR(B_TOK), 4); mbar_init(BAR(B_X1FREE), 4); mbar_init(BAR(B_KVDONE), 8); mbar_init(BAR(B_RAWFULL), 1);
    for (int s = 0; s < 4; s++) { mbar_init(BAR(B_AGRP + s), 8); mbar_init(BAR(B_FULL2 + s), 1); mbar_init(BAR(B_EMPTY2 + s), 4); }
    mbar_init(BAR(B_XRES), 1);
    TSP(59);
  }
  if (warp == 8 || warp == 9) { asm volatile("fence.mbarrier_init.release.cluster;" ::: "memory"); fence_async_smem(); }
  unsigned epoch = 0;
  if (warp >= 8) { epoch = g_epoch[blockIdx.x]; if (tid == 288) sts32(bar + 496, epoch); }
  __syncwarp();
  asm volatile("barrier.cluster.arrive.relaxed.aligned;" ::: "memory");
  cluster_wait();
  if (tid == 0) TSP(62);

  if (warp >= 8) {
    asm volatile("setmaxnreg.dec.sync.aligned.u32 40;");
    if (warp == 8) {
      if (lane == 0) {
        const CUtensorMap* mgu = rank ? &P.w3 : &P.w1;
        uint32_t sl = 0, par = 1;
        auto wtile = [&](int n, const CUtensorMap*& m, int& c, int& r) {
          if (n < 24) { m = n < 8 ? &P.wqkv : mgu; c = n < 8 ? 512 + 512 * rank + 64 * j : f0 + 8 * (n & 16) / 2; r = 64 * (n & 7); }
          else if (n < 32) { m = rank ? &P.w3t : &P.w1t; c = f0 + 128; r = 64 * (n - 24); }
          else { m = &P.wqkv; c = 64 * j; r = 64 * (2 * (n - 32) + rank); }
        };
#pragma unroll 1
        for (int n = 0; n < 36; n++) {
          const CUtensorMap* m; int c, r;
          wtile(n, m, c, r);
          const uint32_t dst = sb + sl * 16384 + rank * 8192, fb = BAR(B_FULL + sl);
          if (n == 4) mbar_wait(BAR(B_XFREE), 0);
          if (n == 16) mbar_wait(BAR(B_AFREE), 0);
          mbar_wait(BAR(B_EMPTY + sl), par);
          tma_ld_mc(dst, m, c, r, fb, (uint16_t)3);
          mbar_expect_tx(fb, (n >= 24 && n < 32) ? 12288 : 16384);
          sl++;
          if (sl == 8) { par ^= 1; if (n < 8) sl = 0; } else if (sl == 12) sl = 0;
        }
        const int cn0 = 128 * c2 + 64 * rank, r2 = i2 * 128;
#pragma unroll 1
        for (int p = 0; p < 16; p++) {
          const int ph = p >> 2, ms = p & 3, j0 = 2 * ms;
          const uint32_t sB = sb + (ms == 3 ? 1u : 4u + 3 * ms) * 16384, sA0 = sB + 16384 + rank * 8192;
          const uint32_t sA1 = ms == 2 ? sb + rank * 8192 : sA0 + 16384, fb = BAR(B_FULL2 + ms);
          const CUtensorMap* m = (ph == 3) ? &P.wo : (ph == 2 ? &P.w2t : &P.w2);
          const CUtensorMap* ma = ph == 2 ? &P.act_t : &P.act_st;
          const int rb0 = (ph == 3) ? 64 * j0 : chunk_f0(j0) + 64 * ph, rb1 = (ph == 3) ? 64 * j0 + 64 : chunk_f0(j0 + 1) + 64 * ph;
          const int ca = (ph == 3) ? 64 * j0 : 512 + 192 * j0 + 64 * ph, ca1 = ca + ((ph == 3) ? 64 : 192);
          if (ms == 0) mbar_wait(BAR(B_AGRP + ph), 0);
          if (ph == 0) {
#pragma unroll 1
            for (int e = 0; e < 3; e++) { mbar_wait(BAR(B_EMPTY + sl), par); sl++; if (sl == 8) par ^= 1; else if (sl == 12) sl = 0; }
          } else mbar_wait(BAR(B_EMPTY2 + ms), (ph - 1) & 1);
          tma_ld_mc(sA0, ma, ca, r2 + 64 * rank, fb, (uint16_t)3);
          tma_ld(sB, m, cn0, rb0, fb);
          tma_ld_mc(sA1, ma, ca1, r2 + 64 * rank, fb, (uint16_t)3);
          tma_ld(sB + 8192, m, cn0, rb1, fb);
          mbar_expect_tx(fb, ph == 2 ? 36864 : 49152);
          if (ms == 3) TSP(51 + ph);
        }
        mbar_wait(BAR(B_EMPTY2), 1);
        mbar_expect_tx(BAR(B_XRES), 16384);
        tma_ld(sb + 4 * 16384, &P.x, cn0, r2, BAR(B_XRES));
        tma_ld(sb + 4 * 16384 + 8192, &P.x, cn0, r2 + 64, BAR(B_XRES));
      }
    } else if (warp == 9) {
#pragma unroll
      for (int hh = 0; hh < 4; hh++) {
        const uint4 v = __ldg(reinterpret_cast<const uint4*>(w_phi + (4 * j + hh) * 256) + lane);
        sts128(sb + OFF_WPF + hh * 512 + (lane >> 4) * 256 + (lane & 1) * 128 + ((lane >> 1) & 7) * 16, v.x, v.y, v.z, v.w);
      }
      fence_async_smem();
      __syncwarp();
      if (lane == 0) mbar_arrive(BAR(B_WPREADY));
      if (ib == 0) {
        float4* z = reinterpret_cast<float4*>(&g_kv[(epoch + 1) & 1][4 * j][0]);
        for (int e = lane; e < 4 * 544 / 4; e += 32) z[e] = make_float4(0.f, 0.f, 0.f, 0.f);
      }
      if (lane == 0) {
        mbar_wait(BAR(B_KVDONE), 0);
        __threadfence();
        red_release_add(&g_kvflag[j * 32], 1u);
        TSP(48);
        flag_wait(&g_kvflag[j * 32], 16u * (epoch + 1));
        TSP(49);
        fence_async_all();
        mbar_expect_tx(BAR(B_RAWFULL), 8704);
        bulk_ld(sb + OFF_RAW, &g_kv[epoch & 1][4 * j][0], 8704, BAR(B_RAWFULL));
      }
      __syncwarp();
      mbar_wait(BAR(B_RAWFULL), 0);
#pragma unroll 1
      for (int hh = 0; hh < 4; hh++) {
        const uint32_t kv = sb + OFF_RAW + hh * 2176;
        const float4 v0 = lds128f(kv + lane * 64), v1 = lds128f(kv + lane * 64 + 16), v2 = lds128f(kv + lane * 64 + 32), v3 = lds128f(kv + lane * 64 + 48);
        const float z = lds32f(kv + 2048 + lane * 4);
        const uint32_t zz = pack2(z, z);
        const uint32_t dst = sb + OFF_KVF + hh * 1536 + (lane >> 3) * 384 + (lane & 7) * 16;
        sts128(dst, pack2(v0.x, v0.y), pack2(v0.z, v0.w), pack2(v1.x, v1.y), pack2(v1.z, v1.w));
        sts128(dst + 128, pack2(v2.x, v2.y), pack2(v2.z, v2.w), pack2(v3.x, v3.y), pack2(v3.z, v3.w));
        sts128(dst + 256, zz, zz, zz, zz);
      }
      fence_async_smem();
      __syncwarp();
      if (lane == 0) { mbar_arrive(BAR(B_KVREADY)); TSP(50); }
      if (lane < 8) {
#pragma unroll 1
        for (int ph = 0; ph < 4; ph++) {
          const int kind = ph;
          flag_wait(&g_aflag[((i2 * 8 + lane) * 4 + kind) * 8], 2u * (epoch + 1));
          fence_async_all();
          mbar_arrive(BAR(B_AGRP + ph));
        }
      }
    } else {
      const int w = warp - 10;
      if (lane == 0) {
        if (w == 0) { prefetch_tmap(&P.w1); prefetch_tmap(&P.w3); prefetch_tmap(&P.act_st); prefetch_tmap(&P.w1t); prefetch_tmap(&P.w3t); prefetch_tmap(&P.act_t); }
        else { prefetch_tmap(&P.w2t); prefetch_tmap(&P.w2); prefetch_tmap(&P.wo); prefetch_tmap(&P.x); }
#pragma unroll 1
        for (int u = 0; u < 4; u++) {
          const int kind = u;
          mbar_wait(BAR(B_STGFULL + w), u & 1);
          const int c = (kind == 3) ? 64 * j : 512 + 192 * j + 64 * kind;
#define TSS(i)
          TSS(0);
          if (u == 0 && w == 1) {
            l2_prefetch(pf_w2 + (size_t)blockIdx.x * 11008, 11008);
            l2_prefetch(pf_wo + (size_t)blockIdx.x * 4096, 4096);
          }
          tma_st(kind == 2 ? &P.act_t : &P.act_st, c, ib * 128 + w * 64, sb + OFF_STG + w * 8192);
          bulk_commit();
          bulk_wait_read();
          TSS(1);
          mbar_arrive(BAR(B_STGEMPTY + w));
          bulk_wait_all();
          TSS(2);
          red_relaxed_add(&g_aflag[((ib * 8 + j) * 4 + kind) * 8], 1u);
          TSS(4);
          if (w == 0) TSP(55 + u);
        }
      }
    }
    __syncwarp();
    asm volatile("barrier.cluster.arrive.relaxed.aligned;" ::: "memory");
    cluster_wait();
    if (tid == 256) g_epoch[blockIdx.x] = epoch + 1;
  } else {
    asm volatile("setmaxnreg.inc.sync.aligned.u32 232;");
    const int wg = warp >> 2, wq = warp & 3;
    const int g = lane >> 2, t = lane & 3;
    const uint32_t peer = rank ^ 1;
    const uint32_t rbar = mapa(bar, peer);
    const uint32_t relbar = mapa(bar + B_EMPTY * 8, wq == 0 ? rank : peer);
    const int mrow = wq * 16 + (lane & 7) + ((lane >> 3) & 1) * 8;
    const uint32_t mo = sb + mrow * 128 + (((mrow & 7) ^ (lane >> 4)) << 4);
    auto MADDR = [&](uint32_t base, uint32_t chunk) { return (mo + (base - sb)) ^ (chunk << 4); };
    const bool releaser = (lane == 0 && wq < 2);
    auto release = [&](uint32_t slot) {
      if (releaser) mbar_arrive_cluster(relbar + slot * 8);
    };
    const uint32_t dlo0 = ((sb & 0x3FFFF) >> 4) | (512u << 16);
    auto stage = [&](uint32_t slot, uint32_t par) { mbar_wait(BAR(B_FULL + slot), par); };

    uint32_t xa[128];
    float rinv0, rinv1;
    {
      TS(wg * 24 + 0);
      const uint32_t xbase = wg ? sb + OFF_A : sb + OFF_W + 4 * 16384;
      float cs[2][4], ca[2][4], cb[2][4];
#pragma unroll
      for (int c = 0; c < 4; c++) { cs[0][c] = cs[1][c] = ca[0][c] = ca[1][c] = cb[0][c] = cb[1][c] = 0.f; }
#pragma unroll
      for (int hf = 0; hf < 2; hf++) {
        mbar_wait(BAR(B_XFULL + 2 * wg + hf), 0);
        if (hf) TS(wg * 24 + 1);
#pragma unroll
        for (int q = 16 * hf; q < 16 * hf + 16; q++)
          ldsm_x4(xa[4 * q], xa[4 * q + 1], xa[4 * q + 2], xa[4 * q + 3], MADDR(xbase + (q >> 2) * 8192, (q & 3) * 2));
        if (hf) {
          __syncwarp();
          if (lane == 0) {
            if (wg == 0) { mbar_arrive(BAR(B_XFREE)); mbar_arrive_cluster(rbar + B_XFREE * 8); }
          }
        }
#pragma unroll
        for (int q = 16 * hf; q < 16 * hf + 16; q++) {
          mma16816(cs[q & 1], xa[4 * q], xa[4 * q + 1], xa[4 * q + 2], xa[4 * q + 3], 0x3F803F80u, 0x3F803F80u);
          mma16816(ca[q & 1], xa[4 * q], xa[4 * q + 1], xa[4 * q + 2], xa[4 * q + 3], xa[4 * q], xa[4 * q + 2]);
          mma16816(cb[q & 1], xa[4 * q], xa[4 * q + 1], xa[4 * q + 2], xa[4 * q + 3], xa[4 * q + 1], xa[4 * q + 3]);
        }
      }
      const int src = (lane & ~3) | (g >> 1), od = g & 1;
      const float q0 = __shfl_sync(0xffffffffu, od ? ca[0][1] + ca[1][1] : ca[0][0] + ca[1][0], src);
      const float q1 = __shfl_sync(0xffffffffu, od ? cb[0][3] + cb[1][3] : cb[0][2] + cb[1][2], src);
      const float a0 = cs[0][0] + cs[1][0], a1 = cs[0][2] + cs[1][2];
      if (wg == 1 && lane == 0) mbar_arrive(BAR(B_X1FREE));
      const float mean0 = a0 * (1.0f / 512.0f), mean1 = a1 * (1.0f / 512.0f);
      const uint32_t m0 = pack2(mean0, mean0), m1 = pack2(mean1, mean1);
#pragma unroll
      for (int q = 0; q < 64; q++) { xa[2 * q] = hsub2_bf16(xa[2 * q], m0); xa[2 * q + 1] = hsub2_bf16(xa[2 * q + 1], m1); }
      const float v0 = bf_round(fmaxf(fmaf(-mean0, mean0, q0 * (1.0f / 512.0f)), 0.f));
      const float v1 = bf_round(fmaxf(fmaf(-mean1, mean1, q1 * (1.0f / 512.0f)), 0.f));
      rinv0 = 1.0f / bf_round(sqrtf(bf_round(v0 + 1e-5f)));
      rinv1 = 1.0f / bf_round(sqrtf(bf_round(v1 + 1e-5f)));
    }
    if (wg == 1) mbar_wait(BAR(B_TOK), 0);
    else mbar_wait(BAR(B_X1FREE), 0);

    const uint32_t stg = sb + OFF_STG + wg * 8192;
    TS(wg * 24 + 2);
#define TOK_KB 4
#define XA(KB, KS) xa[KB * 16 + KS * 4], xa[KB * 16 + KS * 4 + 1], xa[KB * 16 + KS * 4 + 2], xa[KB * 16 + KS * 4 + 3]
#define MMA128(F, SO, KB, KS) wgmma_rs_n128##F<SO + KS * 128, 0x40000040u>(acc, XA(KB, KS), dlo0);
#define P1_STEP(T, KB)                                                               \
        if (KB >= 2) wg_wait<1>();                                                   \
        wg_fence();                                                                  \
        { constexpr int so = ring_slot(8 * T + KB) * 1024;                           \
          if (KB == 0) { MMA128(_first, so, KB, 0) } else { MMA128(, so, KB, 0) }    \
          MMA128(, so, KB, 1) MMA128(, so, KB, 2) MMA128(, so, KB, 3) }              \
        wg_commit();                                                                 \
        TS3(T * 8 + KB);                                                             \
        if (T == 0 && KB == TOK_KB && wg == 0 && lane == 0) mbar_arrive(BAR(B_TOK)); \
        if (KB >= 2) release(ring_slot(8 * T + KB - 2));                             \
        if (KB < 7) stage(ring_slot(8 * T + KB + 1), ring_par(8 * T + KB + 1));
#define P1_KLOOP(T)                                                                  \
      stage(ring_slot(8 * T), ring_par(8 * T));                                      \
      P1_STEP(T, 0) P1_STEP(T, 1) P1_STEP(T, 2) P1_STEP(T, 3)                        \
      P1_STEP(T, 4) P1_STEP(T, 5) P1_STEP(T, 6) P1_STEP(T, 7)                        \
      wg_wait<1>();                                                                  \
      release(ring_slot(8 * T + 6));                                                 \
      wg_wait<0>();                                                                  \
      release(ring_slot(8 * T + 7));
#define GU_CONSTS const float gca = -L2E * rinv0, gcb = -L2E * rinv1, gra = rinv0 * rinv0, grb = rinv1 * rinv1;
    {
      float acc[64];
      P1_KLOOP(0)
      TS(wg * 24 + 3);
      const uint32_t pk_base = sb + OFF_A + wg * 32768;
      const uint32_t v_base = pk_base + 16384;
      mbar_wait(BAR(B_WPREADY), 0);
      if (wg == 0) mbar_wait(BAR(B_X1FREE), 0);
      uint32_t r[4][4], mx[4], mn[4];
      {
#pragma unroll
        for (int np = 0; np < 4; np++) {
          const int q = 32 + 8 * np;
          stsm_x4(MADDR(v_base + (np >> 1) * 8192, 2 * (np & 1)), pack2(acc[q] * rinv0, acc[q + 1] * rinv0), pack2(acc[q + 2] * rinv1, acc[q + 3] * rinv1),
                  pack2(acc[q + 4] * rinv0, acc[q + 5] * rinv0), pack2(acc[q + 6] * rinv1, acc[q + 7] * rinv1));
        }
        {
          const uint32_t rw = wq * 16 + (lane & 15);
          sts128(v_base + (lane >> 4) * 8192 + rw * 128 + ((4 ^ (rw & 7)) << 4), 0x3F803F80u, 0x3F803F80u, 0x3F803F80u, 0x3F803F80u);
        }
        uint32_t a[4][4];
#pragma unroll
        for (int h = 0; h < 4; h++) {
          const int q = 8 * h;
          a[h][0] = pack2(acc[q] * rinv0, acc[q + 1] * rinv0);     a[h][1] = pack2(acc[q + 2] * rinv1, acc[q + 3] * rinv1);
          a[h][2] = pack2(acc[q + 4] * rinv0, acc[q + 5] * rinv0); a[h][3] = pack2(acc[q + 6] * rinv1, acc[q + 7] * rinv1);
        }
        float pp[4][8];
        hh_project_issue(a, sb + OFF_WPF, pp);
        wg_wait<0>();
        hh_project_finish(pp, r, mx, mn);
      }
#pragma unroll
      for (int hp = 0; hp < 2; hp++) {
        uint32_t pos[2][4], neg[2][4];
        hh_softmax2(r, mx, mn, 2 * hp, pos, neg);
#pragma unroll
        for (int u = 0; u < 2; u++) {
          stsm_x4(MADDR(pk_base + hp * 8192, u * 4), pos[u][0], pos[u][1], pos[u][2], pos[u][3]);
          stsm_x4(MADDR(pk_base + hp * 8192, u * 4 + 2), neg[u][0], neg[u][1], neg[u][2], neg[u][3]);
        }
      }
      fence_async_smem();
      named_bar(1 + wg, 128);
      const int hsel = wq >> 1;
      const int f = (wq & 1) * 16 + g;
      float kv[2][20];
      {
        const uint32_t alo = (pk_base & 0x3FFFF) >> 4;
        wg_fence();
        wgmma_tt_n40_first<0, 1024>(kv[0], alo, alo);   wgmma_tt_n40_first<512, 1536>(kv[1], alo, alo);
        wgmma_tt_n40<128, 1152>(kv[0], alo, alo);       wgmma_tt_n40<640, 1664>(kv[1], alo, alo);
        wgmma_tt_n40<256, 1280>(kv[0], alo, alo);       wgmma_tt_n40<768, 1792>(kv[1], alo, alo);
        wgmma_tt_n40<384, 1408>(kv[0], alo, alo);       wgmma_tt_n40<896, 1920>(kv[1], alo, alo);
        wg_commit();
        wg_wait<0>();
      }
      if (lane == 0) { mbar_arrive(BAR(B_AFREE)); mbar_arrive_cluster(rbar + B_AFREE * 8); }
#pragma unroll
      for (int p = 0; p < 2; p++) {
        float* base = &g_kv[lds32(bar + 496) & 1][4 * j + 2 * p + hsel][0];
#pragma unroll
        for (int c = 0; c < 2; c++) {
          const int q = 4 * c;
          const float a0 = hsel ? kv[p][q + 8] : kv[p][q], a1 = hsel ? kv[p][q + 9] : kv[p][q + 1];
          const float a2 = hsel ? kv[p][q + 10] : kv[p][q + 2], a3 = hsel ? kv[p][q + 11] : kv[p][q + 3];
          red_add_v2(base + f * 16 + 8 * c + 2 * t, a0, a1);
          red_add_v2(base + (f + 8) * 16 + 8 * c + 2 * t, a2, a3);
        }
        if (t == 0) { red_add(base + 512 + f, kv[p][16]); red_add(base + 512 + f + 8, kv[p][18]); }
      }
      __syncwarp();
      if (lane == 0) mbar_arrive(BAR(B_KVDONE));
      TS(wg * 24 + 4);
    }
#pragma unroll 1
    for (int tile = 1; tile < 3; tile++) {
      float acc[64];
      if (tile == 1) { P1_KLOOP(1) } else { P1_KLOOP(2) }
      TS(wg * 24 + 3 + 2 * tile);
      GU_CONSTS
      if (tile == 2) mbar_wait(BAR(B_STGEMPTY + wg), 0);
#pragma unroll
      for (int np = 0; np < 4; np++) {
        const int q = 8 * np;
        stsm_x4(MADDR(stg, 2 * np),
                swiglu2(acc[q], acc[q + 1], acc[32 + q], acc[33 + q], gca, gra),
                swiglu2(acc[q + 2], acc[q + 3], acc[34 + q], acc[35 + q], gcb, grb),
                swiglu2(acc[q + 4], acc[q + 5], acc[36 + q], acc[37 + q], gca, gra),
                swiglu2(acc[q + 6], acc[q + 7], acc[38 + q], acc[39 + q], gcb, grb));
      }
      fence_async_smem();
      __syncwarp();
      if (lane == 0) mbar_arrive(BAR(B_STGFULL + wg));
      TS(wg * 24 + 4 + 2 * tile);
    }

    {
      float ag[24], au[24];
#define MMAG(F, SG, KB, KS) wgmma_rs_n48##F<SG + KS * 128, 0x40000040u>(ag, XA(KB, KS), dlo0); wgmma_rs_n48##F<SG + 512 + KS * 128, 0x40000040u>(au, XA(KB, KS), dlo0);
#define G_STEP(KB)                                                                    \
      if (KB >= 2) wg_wait<1>();                                                      \
      wg_fence();                                                                     \
      { constexpr int sg = ring_slot(24 + KB) * 1024;                                 \
        if (KB == 0) { MMAG(_first, sg, KB, 0) } else { MMAG(, sg, KB, 0) }           \
        MMAG(, sg, KB, 1) MMAG(, sg, KB, 2) MMAG(, sg, KB, 3) }                       \
      wg_commit();                                                                    \
      TS3(32 + KB);                                                                   \
      if (KB >= 2) release(ring_slot(22 + KB));                                       \
      if (KB < 7) stage(ring_slot(25 + KB), ring_par(25 + KB));
      stage(ring_slot(24), ring_par(24));
      G_STEP(0) G_STEP(1) G_STEP(2) G_STEP(3) G_STEP(4) G_STEP(5) G_STEP(6) G_STEP(7)
      wg_wait<1>();
      release(ring_slot(30));
      wg_wait<0>();
      release(ring_slot(31));
      TS(wg * 24 + 11);
      const uint32_t keep = ((j & 3) == 3) ? 0u : 0xffffffffu;
      GU_CONSTS
      mbar_wait(BAR(B_STGEMPTY + wg), 1);
#pragma unroll
      for (int np = 0; np < 3; np++) {
        const int q = 8 * np;
        const uint32_t m = np == 2 ? keep : 0xffffffffu;
        stsm_x4(MADDR(stg, 2 * np),
                m & swiglu2(ag[q], ag[q + 1], au[q], au[q + 1], gca, gra), m & swiglu2(ag[q + 2], ag[q + 3], au[q + 2], au[q + 3], gcb, grb),
                m & swiglu2(ag[q + 4], ag[q + 5], au[q + 4], au[q + 5], gca, gra), m & swiglu2(ag[q + 6], ag[q + 7], au[q + 6], au[q + 7], gcb, grb));
      }
      fence_async_smem();
      __syncwarp();
      if (lane == 0) mbar_arrive(BAR(B_STGFULL + wg));
      TS(wg * 24 + 12);
    }
    float as[32], af[32];
    int pr = 0;
    uint32_t db, da0, da1;
    auto kpair_begin = [&]() {
      const uint32_t ms = pr & 3;
      db = dlo0 + (ms == 3 ? 1u : 4u + 3 * ms) * 1024;
      da0 = db + 1024 + wg * 512;
      da1 = ms == 2 ? dlo0 + wg * 512 : da0 + 1024;
      mbar_wait(BAR(B_FULL2 + ms), (pr >> 2) & 1);
      wg_fence();
    };
    auto kpair_done = [&]() {
      wg_commit();
      wg_wait<1>();
      if (pr >= 1 && pr <= 13 && releaser) mbar_arrive_cluster(relbar + (B_EMPTY2 - B_EMPTY + ((pr - 1) & 3)) * 8);
      pr++;
    };
#define KBLOCK(ACC, FIRST) {                                                                                     \
        kpair_begin();                                                                                           \
        if (FIRST) wgmma_ss_n64_first<0, 0>(ACC, da0, db); else wgmma_ss_n64<0, 0>(ACC, da0, db);                \
        wgmma_ss_n64<2, 128>(ACC, da0, db); wgmma_ss_n64<4, 256>(ACC, da0, db); wgmma_ss_n64<6, 384>(ACC, da0, db); \
        wgmma_ss_n64<0, 512>(ACC, da1, db); wgmma_ss_n64<2, 640>(ACC, da1, db);                                  \
        wgmma_ss_n64<4, 768>(ACC, da1, db); wgmma_ss_n64<6, 896>(ACC, da1, db);                                  \
        kpair_done(); }
    uint32_t qa[4][4];
    {
      float aq[32];
#define MMAQ(F, SQ, KB, KS) wgmma_rs_n64##F<SQ + (KB & 1) * 512 + KS * 128, 0x40000040u>(aq, XA(KB, KS), dlo0);
#define Q_STEP(ST)                                                                    \
        if (ST == 2) wg_wait<1>();                                                    \
        wg_fence();                                                                   \
        { constexpr int sq = ring_slot(32 + ST) * 1024;                               \
          if (ST == 0) { MMAQ(_first, sq, 2 * ST, 0) } else { MMAQ(, sq, 2 * ST, 0) } \
          MMAQ(, sq, 2 * ST, 1) MMAQ(, sq, 2 * ST, 2) MMAQ(, sq, 2 * ST, 3)           \
          MMAQ(, sq, (2 * ST + 1), 0) MMAQ(, sq, (2 * ST + 1), 1) MMAQ(, sq, (2 * ST + 1), 2) MMAQ(, sq, (2 * ST + 1), 3) } \
        wg_commit();                                                                  \
        TS3(24 + ST);                                                                 \
        if (ST < 3) stage(ring_slot(33 + ST), ring_par(33 + ST));
      stage(ring_slot(32), ring_par(32));
      Q_STEP(0)
      KBLOCK(af, true)
      release(ring_slot(32));
      Q_STEP(1) Q_STEP(2)
      KBLOCK(af, false)
      release(ring_slot(33)); release(ring_slot(34));
      Q_STEP(3)
      KBLOCK(af, false)
      release(ring_slot(35));
      TS(wg * 24 + 9);
#pragma unroll
      for (int h = 0; h < 4; h++) {
        const int q = 8 * h;
        qa[h][0] = pack2(aq[q] * rinv0, aq[q + 1] * rinv0);     qa[h][1] = pack2(aq[q + 2] * rinv1, aq[q + 3] * rinv1);
        qa[h][2] = pack2(aq[q + 4] * rinv0, aq[q + 5] * rinv0); qa[h][3] = pack2(aq[q + 6] * rinv1, aq[q + 7] * rinv1);
      }
    }
    {
      TS(wg * 24 + 14);
      uint32_t r[4][4], mx[4], mn[4];
      {
        float pp[4][8];
        hh_project_issue(qa, sb + OFF_WPF, pp);
        KBLOCK(af, false)
        hh_project_finish(pp, r, mx, mn);
      }
      mbar_wait(BAR(B_KVREADY), 0);
#pragma unroll
      for (int hp = 0; hp < 2; hp++) {
        uint32_t pos[2][4], neg[2][4];
        hh_softmax2(r, mx, mn, 2 * hp, pos, neg);
        const uint32_t kvt = (((sb + OFF_KVF + hp * 3072) & 0x3FFFF) >> 4) | (24u << 16);
        float ndd[2][12];
        wg_fence();
        wgmma_rs_n24_first<0, 8>(ndd[0], pos[0][0], pos[0][1], pos[0][2], pos[0][3], kvt);
        wgmma_rs_n24<48, 8>(ndd[0], neg[0][0], neg[0][1], neg[0][2], neg[0][3], kvt);
        wgmma_rs_n24_first<96, 8>(ndd[1], pos[1][0], pos[1][1], pos[1][2], pos[1][3], kvt);
        wgmma_rs_n24<144, 8>(ndd[1], neg[1][0], neg[1][1], neg[1][2], neg[1][3], kvt);
        wg_commit();
        KBLOCK(af, false)
        if (hp == 0) mbar_wait(BAR(B_STGEMPTY + wg), 0);
#pragma unroll
        for (int u = 0; u < 2; u++) {
          const float* nd = ndd[u];
          const float r0 = rcp(bf_round(nd[8]) + 1e-6f), r1 = rcp(bf_round(nd[10]) + 1e-6f);
          stsm_x4(MADDR(stg, 4 * hp + 2 * u), pack2(nd[0] * r0, nd[1] * r0), pack2(nd[2] * r1, nd[3] * r1),
                  pack2(nd[4] * r0, nd[5] * r0), pack2(nd[6] * r1, nd[7] * r1));
        }
        if (hp == 1) {
          fence_async_smem();
          __syncwarp();
          if (lane == 0) mbar_arrive(BAR(B_STGFULL + wg));
          TS(wg * 24 + 10);
        }
      }
#pragma unroll 1
      for (int i = 0; i < 2; i++) { KBLOCK(af, false) }
      TS(wg * 24 + 16);
#pragma unroll 1
      for (int i = 0; i < 4; i++) {
        kpair_begin();
        wgmma_ss_n64<0, 0>(af, da0, db); wgmma_ss_n64<2, 128>(af, da0, db); wgmma_ss_n64<4, 256>(af, da0, db);
        wgmma_ss_n64<0, 512>(af, da1, db); wgmma_ss_n64<2, 640>(af, da1, db); wgmma_ss_n64<4, 768>(af, da1, db);
        kpair_done();
      }
      TS(wg * 24 + 17);
      KBLOCK(as, true)
      float gv[32];
#pragma unroll
      for (int q = 0; q < 32; q++) gv[q] = silu_f(af[q]);
#pragma unroll 1
      for (int i = 1; i < 4; i++) { KBLOCK(as, false) }
      mbar_wait(BAR(B_XRES), 0);
      wg_wait<0>();
      TS(wg * 24 + 18);
      const int row = wg * 64 + wq * 16 + g;
      const uint32_t xt = sb + 4 * 16384;
      const uint32_t xr0 = xt + row * 128 + t * 4, xr1 = xr0 + 1024;
#pragma unroll
      for (int q = 0; q < 8; q++) {
        const uint32_t sw = (uint32_t)((q ^ g) << 4);
        const uint32_t x0 = lds32(xr0 + sw), x1 = lds32(xr1 + sw);
        sts32(xr0 + sw, pack2(fmaf(as[4 * q], gv[4 * q], bf_lo(x0)), fmaf(as[4 * q + 1], gv[4 * q + 1], bf_hi(x0))));
        sts32(xr1 + sw, pack2(fmaf(as[4 * q + 2], gv[4 * q + 2], bf_lo(x1)), fmaf(as[4 * q + 3], gv[4 * q + 3], bf_hi(x1))));
      }
      __syncwarp();
      {
        const int r0 = wg * 64 + wq * 16 + (lane >> 3), ch = lane & 7;
        __nv_bfloat16* dst = out + (size_t)(i2 * 128 + r0) * DM + 128 * c2 + 64 * rank + ch * 8;
#pragma unroll
        for (int i = 0; i < 4; i++) {
          const int r = r0 + 4 * i;
          stg128(dst + (size_t)i * 4 * DM, lds128(xt + r * 128 + ((ch ^ (r & 7)) << 4)));
        }
      }
      TS(wg * 24 + 20);
    }
    __syncwarp();
    asm volatile("barrier.cluster.arrive.relaxed.aligned;" ::: "memory");
    cluster_wait();
  }
}

typedef CUresult (*PFN_encodeTiled)(CUtensorMap*, CUtensorMapDataType, cuuint32_t, void*, const cuuint64_t*, const cuuint64_t*,
                                    const cuuint32_t*, const cuuint32_t*, CUtensorMapInterleave, CUtensorMapSwizzle,
                                    CUtensorMapL2promotion, CUtensorMapFloatOOBfill);

static void make_map(PFN_encodeTiled enc, CUtensorMap* m, const void* ptr, uint64_t rows, uint64_t cols, uint32_t box_rows,
                     uint32_t box_cols = 64) {
  cuuint64_t gd[2] = {cols, rows};
  cuuint64_t gs[1] = {cols * 2};
  cuuint32_t bx[2] = {box_cols, box_rows};
  cuuint32_t es[2] = {1, 1};
  enc(m, CU_TENSOR_MAP_DATA_TYPE_BFLOAT16, 2, const_cast<void*>(ptr), gd, gs, bx, es, CU_TENSOR_MAP_INTERLEAVE_NONE,
      CU_TENSOR_MAP_SWIZZLE_128B, CU_TENSOR_MAP_L2_PROMOTION_L2_128B, CU_TENSOR_MAP_FLOAT_OOB_FILL_NONE);
}

}

extern "C" void kernel_launch(void* const* d_in, const int* in_sizes, int n_in, void* d_out, int out_size) {
  using namespace hk;
  static PFN_encodeTiled enc = nullptr;
  static void* act_ptr = nullptr;
  if (!enc) {
    void* fn = nullptr;
    cudaDriverEntryPointQueryResult qr;
    cudaGetDriverEntryPoint("cuTensorMapEncodeTiled", &fn, cudaEnableDefault, &qr);
    enc = (PFN_encodeTiled)fn;
    cudaGetSymbolAddress(&act_ptr, g_act);
    cudaFuncSetAttribute(fused_kernel, cudaFuncAttributeMaxDynamicSharedMemorySize, SMEM_BYTES);
  }
  Params P;
  make_map(enc, &P.x, d_in[0], SEQ, DM, 64);
  {
    cuuint64_t gd[3] = {64, SEQ, 8};
    cuuint64_t gs[2] = {DM * 2, 128};
    cuuint32_t bx[3] = {64, 64, 4};
    cuuint32_t es[3] = {1, 1, 1};
    enc(&P.x3, CU_TENSOR_MAP_DATA_TYPE_BFLOAT16, 3, d_in[0], gd, gs, bx, es, CU_TENSOR_MAP_INTERLEAVE_NONE,
        CU_TENSOR_MAP_SWIZZLE_128B, CU_TENSOR_MAP_L2_PROMOTION_L2_128B, CU_TENSOR_MAP_FLOAT_OOB_FILL_NONE);
  }
  make_map(enc, &P.wqkv, d_in[1], DM, 3 * DM, 64);
  make_map(enc, &P.wo, d_in[3], DM, DM, 64);
  make_map(enc, &P.w1, d_in[5], DM, FF, 64);
  make_map(enc, &P.w3, d_in[6], DM, FF, 64);
  make_map(enc, &P.w2, d_in[7], FF, DM, 64);
  make_map(enc, &P.act_st, act_ptr, SEQ, ACT_W, 64);
  make_map(enc, &P.w1t, d_in[5], DM, FF, 64, 48);
  make_map(enc, &P.w3t, d_in[6], DM, FF, 64, 48);
  make_map(enc, &P.w2t, d_in[7], FF, DM, 48);
  make_map(enc, &P.act_t, act_ptr, SEQ, ACT_W, 64, 48);
  fused_kernel<<<NCTA, 384, SMEM_BYTES, cudaStreamPerThread>>>(
      P, (const __nv_bfloat16*)d_in[2], (__nv_bfloat16*)d_out, (const char*)d_in[3], (const char*)d_in[7]);
}
```
